```python
import torch

def _softmax(x, axis=-1):
    return torch.softmax(x, dim=axis)
def _gelu(x):
    return torch.nn.functional.gelu(x, approximate="tanh")
def _silu(x):
    return torch.nn.functional.silu(x)
def _sigmoid(x):
    return torch.sigmoid(x)
def _layernorm(x, axis=-1, eps=1e-5):
    m = x.mean(dim=axis, keepdim=True)
    v = x.var(dim=axis, keepdim=True, unbiased=False)
    return (x - m) / torch.sqrt(v + eps)
def _scatter_add(tgt, idx, src, axis=0):
    return tgt.clone().index_add_(axis, idx, src)
def _segment_sum(src, seg, n):
    out = torch.zeros((n,) + src.shape[1:], dtype=src.dtype)
    return out.index_add_(0, seg, src)
def _pad(x, pw):
    flat = tuple(v for pair in reversed(pw) for v in pair)
    return torch.nn.functional.pad(x, flat)

kernel_name = 'recurrent_scan__linear_attn_block__dense_activation_mish__prompt'

def setup_inputs():

    _w = (lambda a: (lambda t: t.to(torch.bfloat16) if t.is_floating_point() else t)(torch.as_tensor(a)))
    def _A_setup():
        B, S, D = 1, 2048, 512
        return {
            "x": _w((lambda *s: torch.randn(*s, dtype=torch.bfloat16) * 0.05)(B, S, D)),
            "wqkv": _w((lambda *s: torch.randn(*s, dtype=torch.bfloat16) * 0.2)(D, 3 * D)),
            "wo": _w((lambda *s: torch.randn(*s, dtype=torch.bfloat16) * 0.2)(D, D)),
        }
    _A_in = _A_setup()

    def _B_setup():
        B, S, D, F = 1, 2048, 512, 1792
        return {
            "x": _w((lambda *s: torch.randn(*s, dtype=torch.bfloat16) * 0.05)(B, S, D)),
            "w1": _w((lambda *s: torch.randn(*s, dtype=torch.bfloat16) * 0.8)(D, F) * (D ** -0.5)),
            "b1": _w((lambda *s: torch.randn(*s, dtype=torch.bfloat16) * 0.2)(F)),
            "w2": _w((lambda *s: torch.randn(*s, dtype=torch.bfloat16) * 0.1)(F, D) * (F ** -0.5)),
        }
    _B_in = _B_setup()

    return {
        "A_x": _A_in["x"],
        "A_wqkv": _A_in["wqkv"],
        "A_wo": _A_in["wo"],
        "B_x": _B_in["x"],
        "B_w1": _B_in["w1"],
        "B_b1": _B_in["b1"],
        "B_w2": _B_in["w2"],
    }

def reference(A_x, A_wqkv, A_wo, B_x, B_w1, B_b1, B_w2):
    def _A_ref(x, wqkv, wo):
        B, S, D = x.shape
        H = 32; Dh = D // H
        qkv = (lambda x, *d: x.permute(*d))((x @ wqkv).reshape(B, S, 3, H, Dh), 2, 0, 3, 1, 4)
        q, k, v = qkv[0], qkv[1], qkv[2]
        phi = lambda t: torch.where(t > 0, t + 1, torch.exp(t)) + 1e-6
        pq, pk = phi(q), phi(k)
        kv = torch.einsum("bhsd,bhse->bhde", pk, v)
        z = torch.einsum("bhsd->bhd", pk)
        num = torch.einsum("bhqd,bhde->bhqe", pq, kv)
        den = torch.einsum("bhqd,bhd->bhq", pq, z)[..., None] + 1e-6
        o = num / den
        return (lambda x, *d: x.permute(*d))(o, 0, 2, 1, 3).reshape(B, S, D) @ wo

    def _B_ref(x, w1, b1, w2):
        h = torch.einsum("bsd,df->bsf", x, w1) + b1
        sp = torch.log1p(torch.exp(-torch.abs(h))) + torch.where(h > 0, h, torch.zeros_like(h))
        act = h * torch.tanh(sp)
        return torch.einsum("bsf,fd->bsd", act, w2)

    x = A_x
    xn = _layernorm(x, axis=-1)
    s = _A_ref(xn, A_wqkv, A_wo)
    g = _silu(_B_ref(xn, B_w1, B_b1, B_w2))
    return x + s * g
```

```cpp
#include <cuda_runtime.h>
#include <cuda_bf16.h>
#include <cuda.h>
#include <stdint.h>

namespace {

typedef __nv_bfloat16 bf16;

constexpr int kFS = 224;
#define MPAIR false
#define XLSTEP 4
#define PACE 900
#define PACE0 500

constexpr uint32_t SM_X = 0;
constexpr uint32_t SM_RING = 131072;
constexpr uint32_t SLOT = 32768;
constexpr uint32_t SM_STATS = SM_RING + 3 * SLOT;
constexpr uint32_t SM_CB = SM_STATS + 1024;
constexpr uint32_t SM_BAR = SM_CB + 1792;
constexpr uint32_t SM_TOTAL = SM_BAR + 256;

enum {
  B_XFULL = 0,
  B_FULL = 4,
  B_CRDY = 7,
  B_OFULL = 8,
  B_RECV = 10,
  B_PF = 18,
  B_EPOCH = 20,
  B_EMPTY = 21,
  B_XOK = 24,
  B_EXP = 26,
  B_SOK = 29,
  B_ACT = 30,
  B_XL = 31,
  B_NUM = 32
};

struct __align__(128) State {
  float4 kv[32 * 16 * 8];
  float4 z[32 * 8];
  float4 c[1664];
};
static_assert(sizeof(State) % 16 == 0, "state size");
__device__ State g_state[2];
__device__ unsigned g_epoch;
__device__ unsigned g_done;
__device__ unsigned g_err;
__device__ uint4 g_scr[17 * 65536];
#define GT() do { if (never) asm volatile("exit;"); } while (0)

__device__ __forceinline__ uint32_t smem_u32(const void* p) { return (uint32_t)__cvta_generic_to_shared(p); }
__device__ __forceinline__ void mbar_init(uint32_t bar, uint32_t cnt) {
  asm volatile("mbarrier.init.shared::cta.b64 [%0], %1;" ::"r"(bar), "r"(cnt) : "memory");
}
__device__ __forceinline__ void mbar_expect_tx(uint32_t bar, uint32_t bytes) {
  asm volatile("mbarrier.arrive.expect_tx.shared::cta.b64 _, [%0], %1;" ::"r"(bar), "r"(bytes) : "memory");
}
__device__ __forceinline__ void mbar_arrive(uint32_t bar) {
  asm volatile("mbarrier.arrive.shared::cta.b64 _, [%0];" ::"r"(bar) : "memory");
}
__device__ __forceinline__ bool mbar_try(uint32_t bar, uint32_t parity) {
  uint32_t ok;
  asm volatile(
      "{\n.reg .pred p;\nmbarrier.try_wait.parity.shared::cta.b64 p, [%1], %2;\nselp.u32 %0,1,0,p;\n}"
      : "=r"(ok)
      : "r"(bar), "r"(parity)
      : "memory");
  return ok;
}
__device__ __forceinline__ void mbar_wait(uint32_t bar, uint32_t parity) {
#pragma unroll 1
  for (int i = 0; i < (1 << 18); i++)
    if (mbar_try(bar, parity)) return;
}
__device__ __forceinline__ void tma2d(uint32_t dst, const CUtensorMap* m, int c0, int c1, uint32_t bar) {
  asm volatile(
      "cp.async.bulk.tensor.2d.shared::cluster.global.mbarrier::complete_tx::bytes [%0], [%1, {%3, %4}], [%2];" ::"r"(dst),
      "l"(m), "r"(bar), "r"(c0), "r"(c1)
      : "memory");
}
__device__ __forceinline__ void tma2d_mc(uint32_t dst, const CUtensorMap* m, int c0, int c1, uint32_t bar) {
  asm volatile(
      "cp.async.bulk.tensor.2d.shared::cluster.global.mbarrier::complete_tx::bytes.multicast::cluster [%0], [%1, {%3, %4}], [%2], %5;" ::"r"(dst),
      "l"(m), "r"(bar), "r"(c0), "r"(c1), "h"((uint16_t)3)
      : "memory");
}
__device__ __forceinline__ void bulk_load(uint32_t dst, const void* src, uint32_t bytes, uint32_t bar) {
  asm volatile("cp.async.bulk.shared::cluster.global.mbarrier::complete_tx::bytes [%0], [%1], %2, [%3];" ::"r"(dst), "l"(src),
               "r"(bytes), "r"(bar)
               : "memory");
}
__device__ __forceinline__ void bulk_store(void* dst, uint32_t src, uint32_t bytes) {
  asm volatile("cp.async.bulk.global.shared::cta.bulk_group [%0], [%1], %2;\ncp.async.bulk.commit_group;" ::"l"(dst), "r"(src),
               "r"(bytes)
               : "memory");
}
__device__ __forceinline__ void mbar_arrive_remote(uint32_t bar) {
  asm volatile("mbarrier.arrive.relaxed.cluster.shared::cluster.b64 _, [%0];" ::"r"(bar) : "memory");
}
__device__ __forceinline__ void mbar_wait_cluster(uint32_t bar, uint32_t parity) {
#pragma unroll 1
  for (int i = 0; i < (1 << 18); i++) {
    uint32_t ok;
    asm volatile(
        "{\n.reg .pred p;\nmbarrier.try_wait.parity.acquire.cluster.shared::cta.b64 p, [%1], %2;\nselp.u32 %0,1,0,p;\n}"
        : "=r"(ok)
        : "r"(bar), "r"(parity)
        : "memory");
    if (ok) return;
  }
}
__device__ __forceinline__ void st_async128(uint32_t addr, uint32_t a, uint32_t b, uint32_t c, uint32_t d, uint32_t bar) {
  asm volatile("st.async.weak.shared::cluster.mbarrier::complete_tx::bytes.v4.b32 [%0], {%1,%2,%3,%4}, [%5];" ::"r"(addr), "r"(a),
               "r"(b), "r"(c), "r"(d), "r"(bar)
               : "memory");
}
__device__ __forceinline__ void cluster_arrive() { asm volatile("barrier.cluster.arrive.relaxed.aligned;" ::: "memory"); }
__device__ __forceinline__ void cluster_wait() { asm volatile("barrier.cluster.wait.acquire.aligned;" ::: "memory"); }
__device__ __forceinline__ uint4 lds128(uint32_t addr) {
  uint4 v;
  asm volatile("ld.shared.v4.u32 {%0,%1,%2,%3}, [%4];" : "=r"(v.x), "=r"(v.y), "=r"(v.z), "=r"(v.w) : "r"(addr) : "memory");
  return v;
}
__device__ __forceinline__ void prefetch_tmap(const CUtensorMap* m) {
  asm volatile("prefetch.tensormap [%0];" ::"l"(m) : "memory");
}
__device__ __forceinline__ void l2_prefetch(const void* p, uint32_t bytes) {
  asm volatile("cp.async.bulk.prefetch.L2.global [%0], %1;" ::"l"(p), "r"(bytes) : "memory");
}
__device__ __forceinline__ void fence_proxy_async() { asm volatile("fence.proxy.async.shared::cta;" ::: "memory"); }
__device__ __forceinline__ void wg_fence() { asm volatile("wgmma.fence.sync.aligned;" ::: "memory"); }
__device__ __forceinline__ void wg_commit() { asm volatile("wgmma.commit_group.sync.aligned;" ::: "memory"); }
template <int N>
__device__ __forceinline__ void wg_wait() {
  asm volatile("wgmma.wait_group.sync.aligned %0;" ::"n"(N) : "memory");
}
template <int N>
__device__ __forceinline__ void reg_fence(float (&d)[N]) {
#pragma unroll
  for (int i = 0; i < N; i++) asm volatile("" : "+f"(d[i])::"memory");
}
__device__ __forceinline__ void bar_sync(int id, int n) { asm volatile("bar.sync %0, %1;" ::"r"(id), "r"(n) : "memory"); }
__device__ __forceinline__ constexpr uint32_t desc_lo(uint32_t addr, uint32_t lbo) {
  return ((addr & 0x3FFFF) >> 4) | ((lbo >> 4) << 16);
}
template <int V>
struct IC {
  static constexpr int value = V;
};
template <int N, int I = 0, class F>
__device__ __forceinline__ void static_for(F&& f) {
  if constexpr (I < N) {
    f(IC<I>{});
    static_for<N, I + 1>(f);
  }
}
__device__ __forceinline__ float ex2f(float x) {
  float y;
  asm("ex2.approx.ftz.f32 %0, %1;" : "=f"(y) : "f"(x));
  return y;
}
__device__ __forceinline__ float rcpf(float x) {
  float y;
  asm("rcp.approx.ftz.f32 %0, %1;" : "=f"(y) : "f"(x));
  return y;
}
__device__ __forceinline__ float tanhf_approx(float x) {
  float y;
  asm("tanh.approx.f32 %0, %1;" : "=f"(y) : "f"(x));
  return y;
}
__device__ __forceinline__ uint32_t pack2(float lo, float hi) {
  uint32_t r;
  asm("cvt.rn.bf16x2.f32 %0, %1, %2;" : "=r"(r) : "f"(hi), "f"(lo));
  return r;
}
__device__ __forceinline__ float bf_lo(uint32_t v) { return __uint_as_float(v << 16); }
__device__ __forceinline__ float bf_hi(uint32_t v) { return __uint_as_float(v & 0xffff0000u); }
__device__ __forceinline__ uint32_t hadd2(uint32_t a, uint32_t b) {
  uint32_t r;
  asm("add.rn.bf16x2 %0, %1, %2;" : "=r"(r) : "r"(a), "r"(b));
  return r;
}
__device__ __forceinline__ void mma16816(float (&c)[4], uint32_t a0, uint32_t a1, uint32_t a2, uint32_t a3, uint32_t b0,
                                         uint32_t b1) {
  asm volatile(
      "mma.sync.aligned.m16n8k16.row.col.f32.bf16.bf16.f32 {%0,%1,%2,%3}, {%4,%5,%6,%7}, {%8,%9}, {%0,%1,%2,%3};"
      : "+f"(c[0]), "+f"(c[1]), "+f"(c[2]), "+f"(c[3])
      : "r"(a0), "r"(a1), "r"(a2), "r"(a3), "r"(b0), "r"(b1));
}
__device__ __forceinline__ void stsm4(uint32_t addr, uint32_t r0, uint32_t r1, uint32_t r2, uint32_t r3) {
  asm volatile("stmatrix.sync.aligned.m8n8.x4.shared.b16 [%0], {%1,%2,%3,%4};" ::"r"(addr), "r"(r0), "r"(r1), "r"(r2),
               "r"(r3)
               : "memory");
}
__device__ __forceinline__ void ldsm4(uint32_t addr, uint32_t& r0, uint32_t& r1, uint32_t& r2, uint32_t& r3) {
  asm volatile("ldmatrix.sync.aligned.m8n8.x4.shared.b16 {%0,%1,%2,%3}, [%4];" : "=r"(r0), "=r"(r1), "=r"(r2), "=r"(r3) : "r"(addr) : "memory");
}
__device__ __forceinline__ void sts128(uint32_t addr, uint32_t a, uint32_t b, uint32_t c, uint32_t d) {
  asm volatile("st.shared.v4.u32 [%0], {%1,%2,%3,%4};" ::"r"(addr), "r"(a), "r"(b), "r"(c), "r"(d) : "memory");
}
__device__ __forceinline__ float4 lds128f(uint32_t addr) {
  float4 v;
  asm volatile("ld.shared.v4.f32 {%0,%1,%2,%3}, [%4];" : "=f"(v.x), "=f"(v.y), "=f"(v.z), "=f"(v.w) : "r"(addr) : "memory");
  return v;
}
__device__ __forceinline__ float2 lds64f(uint32_t addr) {
  float2 v;
  asm volatile("ld.shared.v2.f32 {%0,%1}, [%2];" : "=f"(v.x), "=f"(v.y) : "r"(addr) : "memory");
  return v;
}
__device__ __forceinline__ void sts64f(uint32_t addr, float a, float b) {
  asm volatile("st.shared.v2.f32 [%0], {%1,%2};" ::"r"(addr), "f"(a), "f"(b) : "memory");
}
__device__ __forceinline__ void red_v2(float* p, float a, float b) {
  asm volatile("red.relaxed.gpu.global.add.v2.f32 [%0], {%1,%2};" ::"l"(p), "f"(a), "f"(b) : "memory");
}
__device__ __forceinline__ void red_v4(float* p, float a, float b, float c, float d) {
  asm volatile("red.relaxed.gpu.global.add.v4.f32 [%0], {%1,%2,%3,%4};" ::"l"(p), "f"(a), "f"(b), "f"(c), "f"(d) : "memory");
}
__device__ __forceinline__ unsigned ld_relaxed(const unsigned* p) {
  unsigned v;
  asm volatile("ld.relaxed.gpu.global.u32 %0, [%1];" : "=r"(v) : "l"(p) : "memory");
  return v;
}
__device__ __forceinline__ uint4 ld_relaxed128(const uint4* p) {
  uint4 v;
  asm volatile("ld.relaxed.gpu.global.v4.u32 {%0,%1,%2,%3}, [%4];" : "=r"(v.x), "=r"(v.y), "=r"(v.z), "=r"(v.w) : "l"(p) : "memory");
  return v;
}
__device__ __forceinline__ float4 ld_relaxed128f(const float4* p) {
  float4 v;
  asm volatile("ld.relaxed.gpu.global.v4.f32 {%0,%1,%2,%3}, [%4];" : "=f"(v.x), "=f"(v.y), "=f"(v.z), "=f"(v.w) : "l"(p) : "memory");
  return v;
}
__device__ __forceinline__ float2 ld_relaxed64f(const float2* p) {
  float2 v;
  asm volatile("ld.relaxed.gpu.global.v2.f32 {%0,%1}, [%2];" : "=f"(v.x), "=f"(v.y) : "l"(p) : "memory");
  return v;
}

template <int TA, int TB, int AOFF, int BOFF, int ACC>
__device__ __forceinline__ void wgmma_n64(float (&d)[32], uint32_t a_lo, uint32_t b_lo) {
  if constexpr (ACC) {
    asm volatile(
        "{\n.reg .pred p;\n.reg .b32 ta, tb;\n.reg .b64 da, db;\nsetp.ne.b32 p, 1, 0;\n"
        "add.u32 ta, %32, %36;\nadd.u32 tb, %33, %37;\n"
        "mov.b64 da, {ta, 0x40000040};\nmov.b64 db, {tb, 0x40000040};\n"
        "wgmma.mma_async.sync.aligned.m64n64k16.f32.bf16.bf16 {%0, %1, %2, %3, %4, %5, %6, %7, %8, %9, %10, %11, %12, %13, %14, %15, %16, %17, %18, %19, %20, %21, %22, %23, %24, %25, %26, %27, %28, %29, %30, %31}, da, db, p, 1, 1, %34, %35;\n}"
        : "+f"(d[0]), "+f"(d[1]), "+f"(d[2]), "+f"(d[3]), "+f"(d[4]), "+f"(d[5]), "+f"(d[6]), "+f"(d[7]), "+f"(d[8]), "+f"(d[9]), "+f"(d[10]), "+f"(d[11]), "+f"(d[12]), "+f"(d[13]), "+f"(d[14]), "+f"(d[15]), "+f"(d[16]), "+f"(d[17]), "+f"(d[18]), "+f"(d[19]), "+f"(d[20]), "+f"(d[21]), "+f"(d[22]), "+f"(d[23]), "+f"(d[24]), "+f"(d[25]), "+f"(d[26]), "+f"(d[27]), "+f"(d[28]), "+f"(d[29]), "+f"(d[30]), "+f"(d[31])
        : "r"(a_lo), "r"(b_lo), "n"(TA), "n"(TB), "n"(AOFF), "n"(BOFF));
  } else {
    asm volatile(
        "{\n.reg .pred p;\n.reg .b32 ta, tb;\n.reg .b64 da, db;\nsetp.ne.b32 p, 0, 0;\n"
        "add.u32 ta, %32, %36;\nadd.u32 tb, %33, %37;\n"
        "mov.b64 da, {ta, 0x40000040};\nmov.b64 db, {tb, 0x40000040};\n"
        "wgmma.mma_async.sync.aligned.m64n64k16.f32.bf16.bf16 {%0, %1, %2, %3, %4, %5, %6, %7, %8, %9, %10, %11, %12, %13, %14, %15, %16, %17, %18, %19, %20, %21, %22, %23, %24, %25, %26, %27, %28, %29, %30, %31}, da, db, p, 1, 1, %34, %35;\n}"
        : "=f"(d[0]), "=f"(d[1]), "=f"(d[2]), "=f"(d[3]), "=f"(d[4]), "=f"(d[5]), "=f"(d[6]), "=f"(d[7]), "=f"(d[8]), "=f"(d[9]), "=f"(d[10]), "=f"(d[11]), "=f"(d[12]), "=f"(d[13]), "=f"(d[14]), "=f"(d[15]), "=f"(d[16]), "=f"(d[17]), "=f"(d[18]), "=f"(d[19]), "=f"(d[20]), "=f"(d[21]), "=f"(d[22]), "=f"(d[23]), "=f"(d[24]), "=f"(d[25]), "=f"(d[26]), "=f"(d[27]), "=f"(d[28]), "=f"(d[29]), "=f"(d[30]), "=f"(d[31])
        : "r"(a_lo), "r"(b_lo), "n"(TA), "n"(TB), "n"(AOFF), "n"(BOFF));
  }
}
template <int TA, int TB, int AOFF, int BOFF, int ACC>
__device__ __forceinline__ void wgmma_n96(float (&d)[48], uint32_t a_lo, uint32_t b_lo) {
  if constexpr (ACC) {
    asm volatile(
        "{\n.reg .pred p;\n.reg .b32 ta, tb;\n.reg .b64 da, db;\nsetp.ne.b32 p, 1, 0;\n"
        "add.u32 ta, %48, %52;\nadd.u32 tb, %49, %53;\n"
        "mov.b64 da, {ta, 0x40000040};\nmov.b64 db, {tb, 0x40000040};\n"
        "wgmma.mma_async.sync.aligned.m64n96k16.f32.bf16.bf16 {%0, %1, %2, %3, %4, %5, %6, %7, %8, %9, %10, %11, %12, %13, %14, %15, %16, %17, %18, %19, %20, %21, %22, %23, %24, %25, %26, %27, %28, %29, %30, %31, %32, %33, %34, %35, %36, %37, %38, %39, %40, %41, %42, %43, %44, %45, %46, %47}, da, db, p, 1, 1, %50, %51;\n}"
        : "+f"(d[0]), "+f"(d[1]), "+f"(d[2]), "+f"(d[3]), "+f"(d[4]), "+f"(d[5]), "+f"(d[6]), "+f"(d[7]), "+f"(d[8]), "+f"(d[9]), "+f"(d[10]), "+f"(d[11]), "+f"(d[12]), "+f"(d[13]), "+f"(d[14]), "+f"(d[15]), "+f"(d[16]), "+f"(d[17]), "+f"(d[18]), "+f"(d[19]), "+f"(d[20]), "+f"(d[21]), "+f"(d[22]), "+f"(d[23]), "+f"(d[24]), "+f"(d[25]), "+f"(d[26]), "+f"(d[27]), "+f"(d[28]), "+f"(d[29]), "+f"(d[30]), "+f"(d[31]), "+f"(d[32]), "+f"(d[33]), "+f"(d[34]), "+f"(d[35]), "+f"(d[36]), "+f"(d[37]), "+f"(d[38]), "+f"(d[39]), "+f"(d[40]), "+f"(d[41]), "+f"(d[42]), "+f"(d[43]), "+f"(d[44]), "+f"(d[45]), "+f"(d[46]), "+f"(d[47])
        : "r"(a_lo), "r"(b_lo), "n"(TA), "n"(TB), "n"(AOFF), "n"(BOFF));
  } else {
    asm volatile(
        "{\n.reg .pred p;\n.reg .b32 ta, tb;\n.reg .b64 da, db;\nsetp.ne.b32 p, 0, 0;\n"
        "add.u32 ta, %48, %52;\nadd.u32 tb, %49, %53;\n"
        "mov.b64 da, {ta, 0x40000040};\nmov.b64 db, {tb, 0x40000040};\n"
        "wgmma.mma_async.sync.aligned.m64n96k16.f32.bf16.bf16 {%0, %1, %2, %3, %4, %5, %6, %7, %8, %9, %10, %11, %12, %13, %14, %15, %16, %17, %18, %19, %20, %21, %22, %23, %24, %25, %26, %27, %28, %29, %30, %31, %32, %33, %34, %35, %36, %37, %38, %39, %40, %41, %42, %43, %44, %45, %46, %47}, da, db, p, 1, 1, %50, %51;\n}"
        : "=f"(d[0]), "=f"(d[1]), "=f"(d[2]), "=f"(d[3]), "=f"(d[4]), "=f"(d[5]), "=f"(d[6]), "=f"(d[7]), "=f"(d[8]), "=f"(d[9]), "=f"(d[10]), "=f"(d[11]), "=f"(d[12]), "=f"(d[13]), "=f"(d[14]), "=f"(d[15]), "=f"(d[16]), "=f"(d[17]), "=f"(d[18]), "=f"(d[19]), "=f"(d[20]), "=f"(d[21]), "=f"(d[22]), "=f"(d[23]), "=f"(d[24]), "=f"(d[25]), "=f"(d[26]), "=f"(d[27]), "=f"(d[28]), "=f"(d[29]), "=f"(d[30]), "=f"(d[31]), "=f"(d[32]), "=f"(d[33]), "=f"(d[34]), "=f"(d[35]), "=f"(d[36]), "=f"(d[37]), "=f"(d[38]), "=f"(d[39]), "=f"(d[40]), "=f"(d[41]), "=f"(d[42]), "=f"(d[43]), "=f"(d[44]), "=f"(d[45]), "=f"(d[46]), "=f"(d[47])
        : "r"(a_lo), "r"(b_lo), "n"(TA), "n"(TB), "n"(AOFF), "n"(BOFF));
  }
}
template <int TA, int TB, int AOFF, int BOFF, int ACC>
__device__ __forceinline__ void wgmma_n128(float (&d)[64], uint32_t a_lo, uint32_t b_lo) {
  if constexpr (ACC) {
    asm volatile(
        "{\n.reg .pred p;\n.reg .b32 ta, tb;\n.reg .b64 da, db;\nsetp.ne.b32 p, 1, 0;\n"
        "add.u32 ta, %64, %68;\nadd.u32 tb, %65, %69;\n"
        "mov.b64 da, {ta, 0x40000040};\nmov.b64 db, {tb, 0x40000040};\n"
        "wgmma.mma_async.sync.aligned.m64n128k16.f32.bf16.bf16 {%0, %1, %2, %3, %4, %5, %6, %7, %8, %9, %10, %11, %12, %13, %14, %15, %16, %17, %18, %19, %20, %21, %22, %23, %24, %25, %26, %27, %28, %29, %30, %31, %32, %33, %34, %35, %36, %37, %38, %39, %40, %41, %42, %43, %44, %45, %46, %47, %48, %49, %50, %51, %52, %53, %54, %55, %56, %57, %58, %59, %60, %61, %62, %63}, da, db, p, 1, 1, %66, %67;\n}"
        : "+f"(d[0]), "+f"(d[1]), "+f"(d[2]), "+f"(d[3]), "+f"(d[4]), "+f"(d[5]), "+f"(d[6]), "+f"(d[7]), "+f"(d[8]), "+f"(d[9]), "+f"(d[10]), "+f"(d[11]), "+f"(d[12]), "+f"(d[13]), "+f"(d[14]), "+f"(d[15]), "+f"(d[16]), "+f"(d[17]), "+f"(d[18]), "+f"(d[19]), "+f"(d[20]), "+f"(d[21]), "+f"(d[22]), "+f"(d[23]), "+f"(d[24]), "+f"(d[25]), "+f"(d[26]), "+f"(d[27]), "+f"(d[28]), "+f"(d[29]), "+f"(d[30]), "+f"(d[31]), "+f"(d[32]), "+f"(d[33]), "+f"(d[34]), "+f"(d[35]), "+f"(d[36]), "+f"(d[37]), "+f"(d[38]), "+f"(d[39]), "+f"(d[40]), "+f"(d[41]), "+f"(d[42]), "+f"(d[43]), "+f"(d[44]), "+f"(d[45]), "+f"(d[46]), "+f"(d[47]), "+f"(d[48]), "+f"(d[49]), "+f"(d[50]), "+f"(d[51]), "+f"(d[52]), "+f"(d[53]), "+f"(d[54]), "+f"(d[55]), "+f"(d[56]), "+f"(d[57]), "+f"(d[58]), "+f"(d[59]), "+f"(d[60]), "+f"(d[61]), "+f"(d[62]), "+f"(d[63])
        : "r"(a_lo), "r"(b_lo), "n"(TA), "n"(TB), "n"(AOFF), "n"(BOFF));
  } else {
    asm volatile(
        "{\n.reg .pred p;\n.reg .b32 ta, tb;\n.reg .b64 da, db;\nsetp.ne.b32 p, 0, 0;\n"
        "add.u32 ta, %64, %68;\nadd.u32 tb, %65, %69;\n"
        "mov.b64 da, {ta, 0x40000040};\nmov.b64 db, {tb, 0x40000040};\n"
        "wgmma.mma_async.sync.aligned.m64n128k16.f32.bf16.bf16 {%0, %1, %2, %3, %4, %5, %6, %7, %8, %9, %10, %11, %12, %13, %14, %15, %16, %17, %18, %19, %20, %21, %22, %23, %24, %25, %26, %27, %28, %29, %30, %31, %32, %33, %34, %35, %36, %37, %38, %39, %40, %41, %42, %43, %44, %45, %46, %47, %48, %49, %50, %51, %52, %53, %54, %55, %56, %57, %58, %59, %60, %61, %62, %63}, da, db, p, 1, 1, %66, %67;\n}"
        : "=f"(d[0]), "=f"(d[1]), "=f"(d[2]), "=f"(d[3]), "=f"(d[4]), "=f"(d[5]), "=f"(d[6]), "=f"(d[7]), "=f"(d[8]), "=f"(d[9]), "=f"(d[10]), "=f"(d[11]), "=f"(d[12]), "=f"(d[13]), "=f"(d[14]), "=f"(d[15]), "=f"(d[16]), "=f"(d[17]), "=f"(d[18]), "=f"(d[19]), "=f"(d[20]), "=f"(d[21]), "=f"(d[22]), "=f"(d[23]), "=f"(d[24]), "=f"(d[25]), "=f"(d[26]), "=f"(d[27]), "=f"(d[28]), "=f"(d[29]), "=f"(d[30]), "=f"(d[31]), "=f"(d[32]), "=f"(d[33]), "=f"(d[34]), "=f"(d[35]), "=f"(d[36]), "=f"(d[37]), "=f"(d[38]), "=f"(d[39]), "=f"(d[40]), "=f"(d[41]), "=f"(d[42]), "=f"(d[43]), "=f"(d[44]), "=f"(d[45]), "=f"(d[46]), "=f"(d[47]), "=f"(d[48]), "=f"(d[49]), "=f"(d[50]), "=f"(d[51]), "=f"(d[52]), "=f"(d[53]), "=f"(d[54]), "=f"(d[55]), "=f"(d[56]), "=f"(d[57]), "=f"(d[58]), "=f"(d[59]), "=f"(d[60]), "=f"(d[61]), "=f"(d[62]), "=f"(d[63])
        : "r"(a_lo), "r"(b_lo), "n"(TA), "n"(TB), "n"(AOFF), "n"(BOFF));
  }
}

template <int TB, int BOFF, int ACC>
__device__ __forceinline__ void wgmma_rs_n128(float (&d)[64], const uint4& a, uint32_t b_lo) {
  if constexpr (ACC) {
    asm volatile(
        "{\n.reg .pred p;\n.reg .b32 tb;\n.reg .b64 db;\nsetp.ne.b32 p, 1, 0;\n"
        "add.u32 tb, %68, %70;\n"
        "mov.b64 db, {tb, 0x40000040};\n"
        "wgmma.mma_async.sync.aligned.m64n128k16.f32.bf16.bf16 {%0, %1, %2, %3, %4, %5, %6, %7, %8, %9, %10, %11, %12, %13, %14, %15, %16, %17, %18, %19, %20, %21, %22, %23, %24, %25, %26, %27, %28, %29, %30, %31, %32, %33, %34, %35, %36, %37, %38, %39, %40, %41, %42, %43, %44, %45, %46, %47, %48, %49, %50, %51, %52, %53, %54, %55, %56, %57, %58, %59, %60, %61, %62, %63}, {%64, %65, %66, %67}, db, p, 1, 1, %69;\n}"
        : "+f"(d[0]), "+f"(d[1]), "+f"(d[2]), "+f"(d[3]), "+f"(d[4]), "+f"(d[5]), "+f"(d[6]), "+f"(d[7]), "+f"(d[8]), "+f"(d[9]), "+f"(d[10]), "+f"(d[11]), "+f"(d[12]), "+f"(d[13]), "+f"(d[14]), "+f"(d[15]), "+f"(d[16]), "+f"(d[17]), "+f"(d[18]), "+f"(d[19]), "+f"(d[20]), "+f"(d[21]), "+f"(d[22]), "+f"(d[23]), "+f"(d[24]), "+f"(d[25]), "+f"(d[26]), "+f"(d[27]), "+f"(d[28]), "+f"(d[29]), "+f"(d[30]), "+f"(d[31]), "+f"(d[32]), "+f"(d[33]), "+f"(d[34]), "+f"(d[35]), "+f"(d[36]), "+f"(d[37]), "+f"(d[38]), "+f"(d[39]), "+f"(d[40]), "+f"(d[41]), "+f"(d[42]), "+f"(d[43]), "+f"(d[44]), "+f"(d[45]), "+f"(d[46]), "+f"(d[47]), "+f"(d[48]), "+f"(d[49]), "+f"(d[50]), "+f"(d[51]), "+f"(d[52]), "+f"(d[53]), "+f"(d[54]), "+f"(d[55]), "+f"(d[56]), "+f"(d[57]), "+f"(d[58]), "+f"(d[59]), "+f"(d[60]), "+f"(d[61]), "+f"(d[62]), "+f"(d[63])
        : "r"(a.x), "r"(a.y), "r"(a.z), "r"(a.w), "r"(b_lo), "n"(TB), "n"(BOFF));
  } else {
    asm volatile(
        "{\n.reg .pred p;\n.reg .b32 tb;\n.reg .b64 db;\nsetp.ne.b32 p, 0, 0;\n"
        "add.u32 tb, %68, %70;\n"
        "mov.b64 db, {tb, 0x40000040};\n"
        "wgmma.mma_async.sync.aligned.m64n128k16.f32.bf16.bf16 {%0, %1, %2, %3, %4, %5, %6, %7, %8, %9, %10, %11, %12, %13, %14, %15, %16, %17, %18, %19, %20, %21, %22, %23, %24, %25, %26, %27, %28, %29, %30, %31, %32, %33, %34, %35, %36, %37, %38, %39, %40, %41, %42, %43, %44, %45, %46, %47, %48, %49, %50, %51, %52, %53, %54, %55, %56, %57, %58, %59, %60, %61, %62, %63}, {%64, %65, %66, %67}, db, p, 1, 1, %69;\n}"
        : "=f"(d[0]), "=f"(d[1]), "=f"(d[2]), "=f"(d[3]), "=f"(d[4]), "=f"(d[5]), "=f"(d[6]), "=f"(d[7]), "=f"(d[8]), "=f"(d[9]), "=f"(d[10]), "=f"(d[11]), "=f"(d[12]), "=f"(d[13]), "=f"(d[14]), "=f"(d[15]), "=f"(d[16]), "=f"(d[17]), "=f"(d[18]), "=f"(d[19]), "=f"(d[20]), "=f"(d[21]), "=f"(d[22]), "=f"(d[23]), "=f"(d[24]), "=f"(d[25]), "=f"(d[26]), "=f"(d[27]), "=f"(d[28]), "=f"(d[29]), "=f"(d[30]), "=f"(d[31]), "=f"(d[32]), "=f"(d[33]), "=f"(d[34]), "=f"(d[35]), "=f"(d[36]), "=f"(d[37]), "=f"(d[38]), "=f"(d[39]), "=f"(d[40]), "=f"(d[41]), "=f"(d[42]), "=f"(d[43]), "=f"(d[44]), "=f"(d[45]), "=f"(d[46]), "=f"(d[47]), "=f"(d[48]), "=f"(d[49]), "=f"(d[50]), "=f"(d[51]), "=f"(d[52]), "=f"(d[53]), "=f"(d[54]), "=f"(d[55]), "=f"(d[56]), "=f"(d[57]), "=f"(d[58]), "=f"(d[59]), "=f"(d[60]), "=f"(d[61]), "=f"(d[62]), "=f"(d[63])
        : "r"(a.x), "r"(a.y), "r"(a.z), "r"(a.w), "r"(b_lo), "n"(TB), "n"(BOFF));
  }
}

constexpr float kLog2e = 1.4426950408889634f;
constexpr float kLn2 = 0.6931471805599453f;
__device__ __forceinline__ float phi_l2(float y) {
  return fmaf(fmaxf(y, 0.f), kLn2, 1e-6f) + ex2f(fminf(y, 0.f));
}
__device__ __forceinline__ float mish_l2(float y) {
  const float u = ex2f(y);
  const float w = fmaf(u, -0.5f, -1.f);
  const float e = fmaf(u, w, -1.f);
  return fmaf(y, rcpf(e), y);
}
__device__ __forceinline__ uint32_t mish2_l2(float y0, float y1) {
  const float u0 = ex2f(fminf(y0, 31.f)), u1 = ex2f(fminf(y1, 31.f));
  const float e0 = fmaf(u0, fmaf(u0, -0.5f, -1.f), -1.f), e1 = fmaf(u1, fmaf(u1, -0.5f, -1.f), -1.f);
  const float r = rcpf(e0 * e1);
  return pack2(fmaf(y0, r * e1, y0), fmaf(y1, r * e0, y1));
}
template <int OFF, bool PAIR, int N>
__device__ __forceinline__ void mish_nb(const float (&acc)[N], uint32_t& o0, uint32_t& o1, const float4& cb, const float2& s0,
                                        const float2& s1) {
  const float y00 = fmaf(s0.x, acc[OFF + 0], fmaf(s0.y, cb.x, cb.y));
  const float y01 = fmaf(s0.x, acc[OFF + 1], fmaf(s0.y, cb.z, cb.w));
  const float y10 = fmaf(s1.x, acc[OFF + 2], fmaf(s1.y, cb.x, cb.y));
  const float y11 = fmaf(s1.x, acc[OFF + 3], fmaf(s1.y, cb.z, cb.w));
  if constexpr (PAIR) {
    o0 = mish2_l2(y00, y01);
    o1 = mish2_l2(y10, y11);
  } else {
    o0 = pack2(mish_l2(y00), mish_l2(y01));
    o1 = pack2(mish_l2(y10), mish_l2(y11));
  }
}
template <int OFF, int N>
__device__ __forceinline__ void send_tile(const float (&acc)[N], uint32_t dst, uint32_t bar) {
#pragma unroll
  for (int q = 0; q < 4; q++)
    st_async128(dst + q * 2048, pack2(acc[OFF + 8 * q + 0], acc[OFF + 8 * q + 1]), pack2(acc[OFF + 8 * q + 2], acc[OFF + 8 * q + 3]),
                pack2(acc[OFF + 8 * q + 4], acc[OFF + 8 * q + 5]), pack2(acc[OFF + 8 * q + 6], acc[OFF + 8 * q + 7]), bar);
}
template <int N>
__device__ __forceinline__ void pack_tile(const float (&acc)[N], uint4 (&k)[4]) {
#pragma unroll
  for (int q = 0; q < 4; q++)
    k[q] = make_uint4(pack2(acc[8 * q + 0], acc[8 * q + 1]), pack2(acc[8 * q + 2], acc[8 * q + 3]),
                      pack2(acc[8 * q + 4], acc[8 * q + 5]), pack2(acc[8 * q + 6], acc[8 * q + 7]));
}
__device__ __forceinline__ void stage_sum(const uint4 (&k)[4], const uint4 (&r)[4], uint32_t dst, uint32_t tag) {
#pragma unroll
  for (int q = 0; q < 4; q++)
    sts128(dst + q * 2048, (hadd2(k[q].x, r[q].x) & ~1u) | tag, hadd2(k[q].y, r[q].y), hadd2(k[q].z, r[q].z),
           hadd2(k[q].w, r[q].w));
}
__device__ __forceinline__ void store_sum(const uint4 (&k)[4], const uint4 (&r)[4], uint4* dst, uint32_t tag) {
#pragma unroll
  for (int q = 0; q < 4; q++)
    dst[q * 128] = make_uint4((hadd2(k[q].x, r[q].x) & ~1u) | tag, hadd2(k[q].y, r[q].y), hadd2(k[q].z, r[q].z),
                              hadd2(k[q].w, r[q].w));
}

__global__ void __launch_bounds__(384, 1)
fused_kernel(const __grid_constant__ CUtensorMap tm_x, const __grid_constant__ CUtensorMap tm_wqkv,
             const __grid_constant__ CUtensorMap tm_w1, const __grid_constant__ CUtensorMap tm_w2,
             const __grid_constant__ CUtensorMap tm_wo, const bf16* __restrict__ x, const bf16* __restrict__ wqkv,
             const bf16* __restrict__ w1, const bf16* __restrict__ b1, const bf16* __restrict__ w2,
             const bf16* __restrict__ wo, bf16* __restrict__ out) {
  extern __shared__ __align__(1024) uint8_t smem_raw[];
  constexpr uint32_t sbd = 1024;
  const uint32_t sb = smem_u32(smem_raw);
  if ((sb & 0xFFFFFFu) != sbd) __trap();
  const int tid = threadIdx.x, warp = tid >> 5, lane = tid & 31;
  const int rb = blockIdx.x >> 3, sl = blockIdx.x & 7;
  const int ownch = sl >> 1, odd = sl & 1;
  uint32_t sbp;
  asm("mapa.shared::cluster.u32 %0, %1, %2;" : "=r"(sbp) : "r"(sb), "r"(odd ^ 1));
  uint4* const scr = reinterpret_cast<uint4*>((reinterpret_cast<uintptr_t>(g_scr) + 0xFFFFFu) & ~(uintptr_t)0xFFFFFu) + (size_t)rb * 65536;
#define BAR(i) (sb + SM_BAR + 8u * (uint32_t)(i))
#define BARP(i) (sbp + SM_BAR + 8u * (uint32_t)(i))

  if (tid == 257) {
    prefetch_tmap(&tm_x);
    prefetch_tmap(&tm_wqkv);
  }
  if (lane == 0) {
#pragma unroll 1
    for (int i = warp; i < B_NUM; i += 12) {
      if (i == B_EPOCH) {
        asm volatile("st.shared.u32 [%0], %1;" ::"r"(BAR(B_EPOCH)), "r"(0) : "memory");
        continue;
      }
      mbar_init(BAR(i), i >= B_EMPTY ? 8 : 1);
      if (i >= B_RECV && i < B_RECV + 5) mbar_expect_tx(BAR(i), 16384);
    }
    asm volatile("fence.mbarrier_init.release.cluster;" ::: "memory");
    fence_proxy_async();
  }
  __syncthreads();
  cluster_arrive();
  if (tid == 256) {
#pragma unroll
    for (int p = 0; p < 1; p++) {
      mbar_expect_tx(BAR(B_XFULL + p), 32768);
      tma2d(sb + SM_X + p * 32768, &tm_x, 128 * p, 128 * rb, BAR(B_XFULL + p));
      tma2d(sb + SM_X + p * 32768 + 16384, &tm_x, 128 * p + 64, 128 * rb, BAR(B_XFULL + p));
      mbar_expect_tx(BAR(B_FULL + p), 24576);
      tma2d(sb + SM_RING, &tm_wqkv, 512 + 64 * sl, 0, BAR(B_FULL));
      tma2d(sb + SM_RING + 8192, &tm_wqkv, 1024 + 64 * sl, 0, BAR(B_FULL));
      tma2d(sb + SM_RING + 16384, &tm_wqkv, 64 * sl, 0, BAR(B_FULL));
    }
  }
  uint4 csv[4], xsv[4];
  const int srow = 128 * rb + 16 * sl + ((tid >> 4) & 15);
  const int cs_chunk = warp * 4 + (lane & 3);
  auto cs_load = [&](bool first) {
    const int ld = first ? 1792 : 1536;
    if (cs_chunk < (first ? 28 : 24)) {
      const int col = first ? kFS * sl + 8 * cs_chunk : (cs_chunk >> 3) * 512 + 64 * sl + 8 * (cs_chunk & 7);
      const bf16* p = (first ? w1 : wqkv) + (size_t)(32 * rb + 4 * (lane >> 2)) * ld + col;
#pragma unroll
      for (int r = 0; r < 4; r++) csv[r] = __ldg(reinterpret_cast<const uint4*>(p + (size_t)r * ld));
    } else {
#pragma unroll
      for (int r = 0; r < 4; r++) csv[r] = make_uint4(0, 0, 0, 0);
    }
  };
  unsigned par0 = 0;
  if (tid == 32) par0 = ld_relaxed(&g_epoch);
  if (warp < 8) {
    const uint4* xp = reinterpret_cast<const uint4*>(x + (size_t)srow * 512) + (tid & 15);
#pragma unroll
    for (int i = 0; i < 4; i++) xsv[i] = __ldg(xp + 16 * i);
    cs_load(false);
  }

  if (warp >= 8) {
    asm volatile("setmaxnreg.dec.sync.aligned.u32 40;");
    int lane, warp;
    asm volatile("mov.u32 %0, %%laneid;" : "=r"(lane));
    asm volatile("mov.u32 %0, %%tid.x;" : "=r"(warp));
    warp >>= 5;
    unsigned par = 0;
    if (warp >= 9) {
#pragma unroll 1
      for (int i = 0; i < (1 << 18) && par == 0; i++)
        asm volatile("ld.volatile.shared.u32 %0, [%1];" : "=r"(par) : "r"(BAR(B_EPOCH)) : "memory");
    }
    auto issue_stage = [&](int ps) {
      const int s = ps - 2;
      const CUtensorMap* m;
      int c0, c1, r0, r1;
      uint32_t off2 = 16384;
      if (ps < 8) {
        m = &tm_wqkv; c0 = 512 + 64 * sl; c1 = c0 + 512; r0 = r1 = 64 * ps; off2 = 8192;
      } else if (s < 14) {
        m = &tm_w1; c0 = kFS * sl + (s < 10 ? 0 : 128); c1 = c0 + 64; r0 = r1 = 128 * ((s - 6) & 3);
      } else if (s < 20) {
        const int ci = s < 18 ? (s & 1) : 2, half = s < 18 ? ((s - 14) >> 1) : (s & 1);
        m = &tm_w2; c0 = 128 * ((ownch + 1 + ci) & 3) + 64 * odd; c1 = c0 ^ 64; r0 = r1 = kFS * sl + 112 * half; off2 = 14336;
      } else if (s == 20 || s == 23) {
        m = &tm_w2; c0 = c1 = 64 * (s == 20 ? (sl ^ 1) : sl); r0 = kFS * sl; r1 = r0 + 112; off2 = 14336;
      } else {
        m = &tm_wo; c0 = 64 * sl; c1 = c0 ^ 64; r0 = r1 = 256 * odd + 128 * (s - 21);
      }
      const int slot = ps % 3;
      if (ps >= 3) mbar_wait(BAR(B_EMPTY + slot), ((ps / 3) - 1) & 1);
      const uint32_t dst = sb + SM_RING + slot * SLOT, fb = BAR(B_FULL + slot);
      mbar_expect_tx(fb, s == 24 ? 16384 : ps < 8 ? 24576 : 2 * off2);
      if (s == 24) {
        tma2d(dst, &tm_x, 64 * sl, 128 * rb, fb);
      } else {
        tma2d(dst, m, c0, r0, fb);
        tma2d(dst + off2, m, c1, r1, fb);
        if (ps < 8) tma2d(dst + 16384, m, 64 * sl, r0, fb);
      }
    };
    State* st = &g_state[par & 1u];
    if (warp == 8) {
      cluster_wait();
      if (lane == 0) {
#pragma unroll 1
        for (int p = 1; p < 4; p++) mbar_expect_tx(BAR(B_XFULL + p), 32768);
        const long long t0 = clock64();
#pragma unroll 1
        for (int s = 1; s < 27; s++) {
          if (s < 3) while (clock64() - t0 < (long long)(s - 1) * PACE + PACE0) {}
          if (s == 2 || s == 3 || s == 5) {
            const int p = (s + 1) >> 1;
            tma2d_mc(sb + SM_X + (2 * p + odd) * 16384, &tm_x, 64 * (2 * p + odd), 128 * rb, BAR(B_XFULL + p));
          }
          issue_stage(s);
        }
      }
    } else if (warp == 9) {
      cluster_wait();
      if (lane == 0) {
        const unsigned old = atomicInc(&g_done, 127u);
        if (old == 127u) *reinterpret_cast<volatile unsigned*>(&g_epoch) = (par & 1u) + 1u;
        mbar_wait(BAR(B_XFULL + 3), 0);
        l2_prefetch(w2 + (size_t)blockIdx.x * 14 * 512, 14 * 1024);
        l2_prefetch(wo + (size_t)blockIdx.x * 2048, 4096);
      }
      __syncwarp();
#pragma unroll 1
      for (int e = 0; e < 2; e++) {
        mbar_wait(BAR(B_ACT), e);
        fence_proxy_async();
        asm volatile("bar.arrive %0, 160;\nbar.arrive %1, 160;" ::"r"(9 + 2 * e), "r"(10 + 2 * e) : "memory");
      }
      if (lane == 0) {
#pragma unroll 1
        for (int e = 0; e < 2; e++) {
          mbar_wait(BAR(B_EXP + e), 0);
          fence_proxy_async();
          bulk_store(scr + 16384 + (ownch * 8 + 2 * ((ownch + 1 + e) & 3) + odd) * 1024, sb + SM_X + (4 + e) * 16384, 16384);
          asm volatile("cp.async.bulk.wait_group.read 0;" ::: "memory");
          mbar_arrive_remote(BARP(B_PF + e));
        }
        asm volatile("cp.async.bulk.wait_group 0;" ::: "memory");
      }
    } else if (warp == 10) {
      const uint32_t tag = (par & 1u) ^ 1u;
      uint4* z = reinterpret_cast<uint4*>(&g_state[(par & 1u) ^ 1u]);
      constexpr int NV = sizeof(State) / 16;
      constexpr int PER = (NV + 127) / 128;
      static_assert(PER <= 64, "state clearing");
#pragma unroll
      for (int i = lane; i < PER; i += 32) {
        const int idx = blockIdx.x * PER + i;
        if (idx < NV) z[idx] = make_uint4(0, 0, 0, 0);
      }
      auto stage_cb = [&](int cp0) {
        const int cp1 = cp0 + 32 < 112 ? cp0 + 32 : cp0;
        const uint32_t bl0 = *reinterpret_cast<const uint32_t*>(b1 + kFS * sl + 2 * cp0);
        const uint32_t bl1 = *reinterpret_cast<const uint32_t*>(b1 + kFS * sl + 2 * cp1);
        const float4 c0 = ld_relaxed128f(st->c + 768 + 112 * sl + cp0), c1 = ld_relaxed128f(st->c + 768 + 112 * sl + cp1);
        sts128(sb + SM_CB + cp0 * 16, __float_as_uint(c0.x), __float_as_uint(bf_lo(bl0) * kLog2e), __float_as_uint(c0.z),
               __float_as_uint(bf_hi(bl0) * kLog2e));
        sts128(sb + SM_CB + cp1 * 16, __float_as_uint(c1.x), __float_as_uint(bf_lo(bl1) * kLog2e), __float_as_uint(c1.z),
               __float_as_uint(bf_hi(bl1) * kLog2e));
        return c0.y == 16.f && c0.w == 16.f && c1.y == 16.f && c1.w == 16.f;
      };
      mbar_wait(BAR(B_XFULL + 1), 0);
#pragma unroll 1
      for (int tries = 0; tries < (1 << 16); tries++) {
        const uint4* sp = scr + lane;
        const uint4 a = ld_relaxed128(sp), b = ld_relaxed128(sp + 32);
        float4 c[3];
#pragma unroll
        for (int i = 0; i < 3; i++) c[i] = ld_relaxed128f(st->c + 256 * i + 32 * sl + lane);
        bool ok = (((a.x ^ tag) | (a.z ^ tag) | (b.x ^ tag) | (b.z ^ tag)) & 1u) == 0u;
        sts128(sb + SM_STATS + lane * 16, a.x, a.y, a.z, a.w);
        sts128(sb + SM_STATS + 512 + lane * 16, b.x, b.y, b.z, b.w);
#pragma unroll
        for (int i = 0; i < 3; i++) {
          ok = ok && c[i].y == 16.f && c[i].w == 16.f;
          sts64f(sb + SM_CB + 1024 + (i * 32 + lane) * 8, c[i].x, c[i].z);
        }
        if (__all_sync(0xffffffffu, ok)) break;
      }
      asm volatile("bar.arrive 13, 288;" ::: "memory");
#pragma unroll 1
      for (int tries = 0; tries < (1 << 16); tries++) {
        if (__all_sync(0xffffffffu, stage_cb(lane))) break;
      }
      __syncwarp();
      if (lane == 0) {
        mbar_arrive(BAR(B_CRDY));
      }
      __syncwarp();
      cluster_wait();
      {
        const unsigned* kc = reinterpret_cast<const unsigned*>(st->kv + (4 * sl) * 128 + lane) + 2;
#pragma unroll 1
        for (int tries = 0; tries < (1 << 16); tries++) {
          unsigned c[18];
#pragma unroll
          for (int i = 0; i < 16; i++) c[i] = ld_relaxed(kc + i * 128);
          c[16] = ld_relaxed(reinterpret_cast<const unsigned*>(st->z + (4 * sl) * 8 + lane) + 1);
          c[17] = ld_relaxed(reinterpret_cast<const unsigned*>(st->z + (4 * sl) * 8 + lane) + 3);
          unsigned bad = 0;
#pragma unroll
          for (int i = 0; i < 18; i++) bad |= c[i] ^ 0x42000000u;
          if (__all_sync(0xffffffffu, bad == 0u)) break;
        }
        uint32_t kb[16];
#pragma unroll
        for (int h2 = 0; h2 < 2; h2++) {
          float2 v[8];
#pragma unroll
          for (int i = 0; i < 8; i++) v[i] = ld_relaxed64f(reinterpret_cast<const float2*>(kc - 2 + (8 * h2 + i) * 128));
#pragma unroll
          for (int i = 0; i < 8; i++) kb[8 * h2 + i] = pack2(v[i].x, v[i].y);
        }
        mbar_wait(BAR(B_ACT), 0);
#pragma unroll
        for (int i = 0; i < 16; i++)
          asm volatile("st.shared.u32 [%0], %1;" ::"r"(sb + SM_STATS + (i * 32 + lane) * 4), "r"(kb[i]) : "memory");
      }
      asm volatile("bar.arrive 14, 288;" ::: "memory");
#pragma unroll 1
      for (int tries = 0; tries < (1 << 16); tries++) {
        if (__all_sync(0xffffffffu, stage_cb(lane + 64))) break;
      }
      asm volatile("bar.arrive 13, 288;" ::: "memory");
    } else {
      if (lane == 0) {
        prefetch_tmap(&tm_w1);
        prefetch_tmap(&tm_w2);
        prefetch_tmap(&tm_wo);
      }
      cluster_wait();
      if (lane == 0) {
#pragma unroll 1
        for (int gq = 0; gq < 2; gq++) {
          mbar_wait(BAR(B_XL), gq);
          mbar_expect_tx(BAR(B_OFULL), 32768);
          bulk_load(sb + SM_X + 6 * 16384, scr + 1024 + (16 * odd + 8 * gq) * 256, 32768, BAR(B_OFULL));
        }
      }
      __syncwarp();
    }
  } else {
  asm volatile("setmaxnreg.inc.sync.aligned.u32 232;");
    const int wg = __shfl_sync(0xffffffffu, warp >> 2, 0);
    const int w = warp & 3, g = lane >> 2, t = lane & 3;
    const uint32_t xw = sb + SM_X + wg * 8192;
    const uint32_t dX = desc_lo(sbd + SM_X, 16) + wg * 512;
    constexpr uint32_t dR = desc_lo(sbd + SM_RING, 0);
#define PH(s) ((s) >= 100 ? (s) - 100 : (s) + 2)
    auto wait_full = [&](int l) {
      const int i = PH(l);
      if (i < 8 && !(i & 1)) mbar_wait(BAR(B_XFULL + (i >> 1)), 0);
      mbar_wait(BAR(B_FULL + i % 3), (i / 3) & 1);
    };
    auto warp_arrive = [&](int b) {
      __syncwarp();
      if (lane == 0) mbar_arrive(BAR(b));
    };
    auto release = [&](int l) { warp_arrive(B_EMPTY + PH(l) % 3); };
#define XO(kk) (((kk) >> 2) * 1024 + ((kk) & 3) * 2)
#define RO(stg, lbo) ((PH(stg) % 3) * (int)(SLOT >> 4) + (((lbo) >> 4) << 16))

    unsigned never_u;
    bool never;
    asm volatile("{\n.reg .pred p;\nsetp.eq.u32 p, %1, 0x7fffffff;\nselp.u32 %0, 1, 0, p;\n}" : "=r"(never_u) : "r"(tid));
    never = never_u != 0;
    auto step_begin = [&](int stage) {
      if (stage >= 0) wait_full(stage);
      GT();
      wg_fence();
    };
    auto step_end = [&](int rel) {
      wg_commit();
      wg_wait<1>();
      if (rel >= 0) release(rel);
    };
    State* st = nullptr;
    uint32_t tag = 0;
    auto get_parity = [&]() {
      if (tid == 32) asm volatile("{\n.reg .b32 t;\nand.b32 t, %1, 1;\nadd.u32 t, t, 2;\nst.volatile.shared.u32 [%0], t;\n}" ::"r"(BAR(B_EPOCH)), "r"(par0) : "memory");
      unsigned par = 0;
#pragma unroll 1
      for (int i = 0; i < (1 << 18) && par == 0; i++)
        asm volatile("ld.volatile.shared.u32 %0, [%1];" : "=r"(par) : "r"(BAR(B_EPOCH)) : "memory");
      st = &g_state[par & 1u];
      tag = (par & 1u) ^ 1u;
    };
    auto cs_finish = [&](bool first) {
      float s[8];
      s[0] = (bf_lo(csv[0].x) + bf_lo(csv[1].x)) + (bf_lo(csv[2].x) + bf_lo(csv[3].x));
      s[1] = (bf_hi(csv[0].x) + bf_hi(csv[1].x)) + (bf_hi(csv[2].x) + bf_hi(csv[3].x));
      s[2] = (bf_lo(csv[0].y) + bf_lo(csv[1].y)) + (bf_lo(csv[2].y) + bf_lo(csv[3].y));
      s[3] = (bf_hi(csv[0].y) + bf_hi(csv[1].y)) + (bf_hi(csv[2].y) + bf_hi(csv[3].y));
      s[4] = (bf_lo(csv[0].z) + bf_lo(csv[1].z)) + (bf_lo(csv[2].z) + bf_lo(csv[3].z));
      s[5] = (bf_hi(csv[0].z) + bf_hi(csv[1].z)) + (bf_hi(csv[2].z) + bf_hi(csv[3].z));
      s[6] = (bf_lo(csv[0].w) + bf_lo(csv[1].w)) + (bf_lo(csv[2].w) + bf_lo(csv[3].w));
      s[7] = (bf_hi(csv[0].w) + bf_hi(csv[1].w)) + (bf_hi(csv[2].w) + bf_hi(csv[3].w));
#pragma unroll
      for (int i = 0; i < 4; i++) {
        const float send = (lane & 16) ? s[i] : s[i + 4], keep = (lane & 16) ? s[i + 4] : s[i];
        s[i] = keep + __shfl_xor_sync(0xffffffffu, send, 16);
      }
#pragma unroll
      for (int i = 0; i < 2; i++) {
        const float send = (lane & 8) ? s[i] : s[i + 2], keep = (lane & 8) ? s[i + 2] : s[i];
        s[i] = keep + __shfl_xor_sync(0xffffffffu, send, 8);
      }
      s[0] += __shfl_xor_sync(0xffffffffu, s[0], 4);
      s[1] += __shfl_xor_sync(0xffffffffu, s[1], 4);
      if ((lane & 4) == 0 && cs_chunk < (first ? 28 : 24)) {
        const int col = first ? 1536 + kFS * sl + 8 * cs_chunk : (cs_chunk >> 3) * 512 + 64 * sl + 8 * (cs_chunk & 7);
        red_v4(reinterpret_cast<float*>(st->c + (col >> 1) + ((lane >> 4) & 1) * 2 + ((lane >> 3) & 1)), s[0], 1.f, s[1], 1.f);
      }
    };
    auto prep_finish = [&]() {
      cs_finish(false);
      {
        const float pivot = __shfl_sync(0xffffffffu, bf_lo(xsv[0].x), lane & 16);
        float sum0 = 0.f, sq0 = 0.f, sum1 = 0.f, sq1 = 0.f;
  #pragma unroll
        for (int i = 0; i < 4; i++) {
          const uint32_t u[4] = {xsv[i].x, xsv[i].y, xsv[i].z, xsv[i].w};
  #pragma unroll
          for (int j = 0; j < 4; j++) {
            const float d0 = bf_lo(u[j]) - pivot, d1 = bf_hi(u[j]) - pivot;
            sum0 += d0; sq0 = fmaf(d0, d0, sq0);
            sum1 += d1; sq1 = fmaf(d1, d1, sq1);
          }
        }
        float sum = sum0 + sum1, sq = sq0 + sq1;
  #pragma unroll
        for (int o = 1; o < 16; o <<= 1) {
          sum += __shfl_xor_sync(0xffffffffu, sum, o);
          sq += __shfl_xor_sync(0xffffffffu, sq, o);
        }
        const float md = sum * (1.f / 512.f);
        const float var = fmaxf(sq * (1.f / 512.f) - md * md, 0.f);
        const float rs = rsqrtf(var + 1e-5f);
        if ((tid & 15) == 0) reinterpret_cast<float2*>(scr)[srow & 127] = make_float2(__uint_as_float((__float_as_uint(rs) & ~1u) | tag), -rs * (pivot + md));
      }
    };
    float accK[32], accV[32], accQ[32];
    const uint32_t cb_ = sb + SM_CB + 16 * t;
    const uint32_t sv_ = sb + SM_STATS + (wg * 64 + 2 * t) * 8;
    static_for<16>([&](auto I) {
      constexpr int i = decltype(I)::value, s = i >> 1, k0 = 2 * (i & 1);
      step_begin((i & 1) == 0 ? 100 + s : -1);
      static_for<2>([&](auto K) {
        constexpr int kk = k0 + decltype(K)::value, acc = (i | decltype(K)::value) != 0;
        wgmma_n64<1, 0, RO(100 + s, 16) + kk * 128, XO(4 * s + kk), acc>(accK, dR, dX);
        wgmma_n64<1, 0, RO(100 + s, 16) + 512 + kk * 128, XO(4 * s + kk), acc>(accV, dR, dX);
        wgmma_n64<0, 1, XO(4 * s + kk), RO(100 + s, 16) + 1024 + kk * 128, acc>(accQ, dX, dR);
      });
      step_end(((i & 1) == 0 && s > 0) ? 99 + s : -1);
      if (i == 2) {
        get_parity();
        prep_finish();
      }
      if (i == 4) cluster_wait();
      if (i == 5) cs_load(true);
      if (i == 12) cs_finish(true);
    });
    float kv0[4] = {0.f, 0.f, 0.f, 0.f}, kv1[4] = {0.f, 0.f, 0.f, 0.f};
    float zs0 = 0.f, zs1 = 0.f;
    bar_sync(13, 288);
    float2 st0 = lds64f(sb + SM_STATS + (wg * 64 + 16 * w + g) * 8);
    float2 st1 = lds64f(sb + SM_STATS + (wg * 64 + 16 * w + g + 8) * 8);
    float4 cb = lds128f(sv_);
    st0.x *= kLog2e; st0.y *= kLog2e; st1.x *= kLog2e; st1.y *= kLog2e;
    float ckv[4];
#pragma unroll
    for (int j = 0; j < 4; j++)
      asm volatile("ld.shared.f32 %0, [%1];" : "=f"(ckv[j]) : "r"(sb + SM_CB + 1024 + (64 + 64 * (j >> 1) + 16 * w + g + 8 * (j & 1)) * 4) : "memory");
    const float ck0 = ckv[0] * kLog2e, ck1 = ckv[1] * kLog2e, cv0 = ckv[2], cv1 = ckv[3];
    uint32_t ka[4], kbf[4];
    auto kv_block = [&](auto NB, const float4& s4) {
      constexpr int nb = decltype(NB)::value, h = nb & 1;
      const float l0 = s4.x * kLog2e, l1 = s4.z * kLog2e;
      const float p00 = phi_l2(fmaf(l0, accK[4 * nb + 0], s4.y * ck0)), p01 = phi_l2(fmaf(l1, accK[4 * nb + 1], s4.w * ck0));
      const float p10 = phi_l2(fmaf(l0, accK[4 * nb + 2], s4.y * ck1)), p11 = phi_l2(fmaf(l1, accK[4 * nb + 3], s4.w * ck1));
      zs0 += p00 + p01;
      zs1 += p10 + p11;
      kbf[h] = pack2(p00, p01);
      kbf[2 + h] = pack2(p10, p11);
      ka[2 * h + 0] = pack2(fmaf(s4.x, accV[4 * nb + 0], s4.y * cv0), fmaf(s4.z, accV[4 * nb + 1], s4.w * cv0));
      ka[2 * h + 1] = pack2(fmaf(s4.x, accV[4 * nb + 2], s4.y * cv1), fmaf(s4.z, accV[4 * nb + 3], s4.w * cv1));
      asm volatile("" : "+r"(kbf[h]), "+r"(kbf[2 + h]), "+r"(ka[2 * h]), "+r"(ka[2 * h + 1]));
      if (h == 1) {
        mma16816(kv0, ka[0], ka[1], ka[2], ka[3], kbf[0], kbf[1]);
        mma16816(kv1, ka[0], ka[1], ka[2], ka[3], kbf[2], kbf[3]);
      }
    };

    float accH[64];
    uint32_t pq[16];
    const float4* zp = st->z + (4 * sl) * 8 + t;
    uint4* odst = scr + 1024 + (4 * sl) * 256 + tid;
    uint32_t kb[16];
    float4 zf[8];
    auto kv_load = [&]() {
      const uint32_t ka = sb + SM_STATS + (g * 8 + t) * 4;
#pragma unroll
      for (int i = 0; i < 16; i++)
        asm volatile("ld.shared.u32 %0, [%1];" : "=r"(kb[i]) : "r"(ka + (i >> 2) * 512 + ((i >> 1) & 1) * 256 + (i & 1) * 16) : "memory");
      bool ok = true;
#pragma unroll
      for (int i = 0; i < 8; i++) ok = ok && zf[i].y == 32.f && zf[i].w == 32.f;
      if (!__all_sync(0xffffffffu, ok)) {
#pragma unroll
        for (int i = 0; i < 8; i++) zf[i] = ld_relaxed128f(zp + (i >> 1) * 8 + (i & 1) * 4);
      }
    };
    float n0[4], n1[4], dn[4];
    auto o_mma = [&](auto HH) {
      constexpr int hh = decltype(HH)::value;
#pragma unroll
      for (int j = 0; j < 4; j++) n0[j] = n1[j] = dn[j] = 0.f;
      mma16816(n0, pq[4 * hh], pq[4 * hh + 1], pq[4 * hh + 2], pq[4 * hh + 3], kb[4 * hh + 0], kb[4 * hh + 1]);
      mma16816(n1, pq[4 * hh], pq[4 * hh + 1], pq[4 * hh + 2], pq[4 * hh + 3], kb[4 * hh + 2], kb[4 * hh + 3]);
      mma16816(dn, pq[4 * hh], pq[4 * hh + 1], pq[4 * hh + 2], pq[4 * hh + 3], pack2(zf[2 * hh].x, zf[2 * hh].z),
               pack2(zf[2 * hh + 1].x, zf[2 * hh + 1].z));
    };
    auto o_store = [&](int hh) {
      const float r0 = rcpf(dn[0] + 1e-6f), r1 = rcpf(dn[2] + 1e-6f);
      uint4 v;
      v.x = (pack2(n0[0] * r0, n0[1] * r0) & ~1u) | tag;
      v.y = pack2(n0[2] * r1, n0[3] * r1);
      v.z = pack2(n1[0] * r0, n1[1] * r0);
      v.w = pack2(n1[2] * r1, n1[3] * r1);
      odst[hh * 256] = v;
    };
    static_for<16>([&](auto I) {
      constexpr int i = decltype(I)::value, s = i >> 2, k0 = 2 * (i & 3);
      float2 cq = make_float2(0.f, 0.f);
      float4 cbn = cb;
      if (i < 7) cbn = lds128f(sv_ + 64 * (i + 1));
      if (i >= 8) cq = lds64f(sb + SM_CB + 1024 + (8 * (i - 8) + 2 * t) * 4);
      step_begin((i & 3) == 0 ? 6 + s : -1);
      wgmma_n128<0, 1, XO(8 * s + k0), RO(6 + s, 16384) + k0 * 128, i != 0>(accH, dX, dR);
      wgmma_n128<0, 1, XO(8 * s + k0 + 1), RO(6 + s, 16384) + (k0 + 1) * 128, 1>(accH, dX, dR);
      step_end((i & 3) == 0 ? 5 + s : -1);
      if (i == 0) {
        reg_fence(accK);
        reg_fence(accV);
        reg_fence(accQ);
      }
      if constexpr (i < 8) kv_block(I, cb);
      cb = cbn;
      if (i == 8) {
        zs0 += __shfl_xor_sync(0xffffffffu, zs0, 1);
        zs1 += __shfl_xor_sync(0xffffffffu, zs1, 1);
        zs0 += __shfl_xor_sync(0xffffffffu, zs0, 2);
        zs1 += __shfl_xor_sync(0xffffffffu, zs1, 2);
      }
      if (i == 9) {
        float* kvw = reinterpret_cast<float*>(st->kv + (4 * sl + w) * 128 + g * 8 + t);
        red_v4(kvw, kv0[0], kv0[1], 1.f, 0.f);
        red_v4(kvw + 256, kv0[2], kv0[3], 1.f, 0.f);
        red_v4(kvw + 16, kv1[0], kv1[1], 1.f, 0.f);
        red_v4(kvw + 272, kv1[2], kv1[3], 1.f, 0.f);
        if (t == 0) {
          float* zw = reinterpret_cast<float*>(st->z + (4 * sl + w) * 8) + 2 * g;
          red_v2(zw, zs0, 1.f);
          red_v2(zw + 16, zs1, 1.f);
        }
      }
      if constexpr (i >= 8) {
        constexpr int nb = i - 8;
        pq[2 * nb + 0] = pack2(phi_l2(fmaf(st0.x, accQ[4 * nb + 0], st0.y * cq.x)), phi_l2(fmaf(st0.x, accQ[4 * nb + 1], st0.y * cq.y)));
        pq[2 * nb + 1] = pack2(phi_l2(fmaf(st1.x, accQ[4 * nb + 2], st1.y * cq.x)), phi_l2(fmaf(st1.x, accQ[4 * nb + 3], st1.y * cq.y)));
        asm volatile("" : "+r"(pq[2 * nb]), "+r"(pq[2 * nb + 1]));
      }
      if (i == 3) bar_sync(1 + wg, 128);
      if (i == 13) mbar_wait(BAR(B_CRDY), 0);
      if (i == 15) cb = lds128f(cb_);
    });

    float accC[48];
    const uint32_t st_addr = xw + (16 * w + (lane & 7) + 8 * ((lane >> 3) & 1)) * 128;
    const int st_hi = lane >> 4, st_r = lane & 7;
    auto st_act = [&](int j, const uint32_t* r) {
      stsm4(st_addr + (j >> 2) * 16384 + (uint32_t)(((2 * (j & 3) + st_hi) ^ st_r) << 4), r[0], r[1], r[2], r[3]);
    };
    uint32_t act[32];
    float4 cbv[3];
    cbv[0] = cb;
    cbv[1] = lds128f(cb_ + 64);
    cbv[2] = lds128f(cb_ + 128);
    static_for<8>([&](auto I) {
      constexpr int i = decltype(I)::value, s = i >> 1, k0 = 4 * (i & 1);
      constexpr int nb0 = i < 4 ? 3 * i : 12 + 2 * (i - 4), cnt = i < 4 ? 3 : (i < 6 ? 2 : 0);
      float4 cbn[3] = {cbv[0], cbv[1], cbv[2]};
#pragma unroll
      for (int j = 0; j < 3; j++)
        if (cnt > 0 && nb0 + cnt + j < 16) cbn[j] = lds128f(cb_ + 64 * (nb0 + cnt + j));
      step_begin((i & 1) == 0 ? 10 + s : -1);
      static_for<4>([&](auto K) {
        constexpr int kk = k0 + decltype(K)::value;
        wgmma_n96<0, 1, XO(8 * s + kk), RO(10 + s, 16384) + kk * 128, (i | decltype(K)::value) != 0>(accC, dX, dR);
      });
      step_end((i & 1) == 0 ? 9 + s : -1);
      if (i == 0) reg_fence(accH);
      static_for<cnt>([&](auto J) {
        constexpr int nb = nb0 + decltype(J)::value;
        mish_nb<4 * nb, true>(accH, act[2 * nb], act[2 * nb + 1], cbv[decltype(J)::value], st0, st1);
      });
      if (i == 1) { st_act(0, &act[0]); st_act(1, &act[4]); st_act(2, &act[8]); }
      if (i == 2) st_act(3, &act[12]);
      if (i == 3) { st_act(4, &act[16]); st_act(5, &act[20]); }
      if (i == 4) st_act(6, &act[24]);
      if (i == 5) {
        st_act(7, &act[28]);
        warp_arrive(B_ACT);
      }
      if (i == 3) {
#pragma unroll
        for (int j = 0; j < 8; j++) zf[j] = ld_relaxed128f(zp + (j >> 1) * 8 + (j & 1) * 4);
      }
      if (i == 6) {
        bar_sync(14, 288);
        kv_load();
        o_mma(IC<0>{});
      }
      if (i == 7) {
        o_store(0);
        o_mma(IC<1>{});
        bar_sync(13, 288);
        cb = lds128f(cb_ + 64 * 16);
      }
#pragma unroll
      for (int j = 0; j < 3; j++) cbv[j] = cbn[j];
    });
    bar_sync(9 + wg, 160);

    float accP[64], accR[64];
    uint4 actC[6];
    auto g2_step = [&](float (&acc)[64], auto S, auto H, auto J) {
      constexpr int stg = decltype(S)::value, half = decltype(H)::value, j = decltype(J)::value;
      step_begin(j == 0 ? stg : -1);
      static_for<(j == 2 ? 3 : 2)>([&](auto K) {
        constexpr int k7 = 2 * j + decltype(K)::value, kk = half * 7 + k7;
        if constexpr (stg < 18 && kk >= 8) wgmma_rs_n128<1, RO(stg, 14336) + k7 * 128, 1>(acc, actC[kk - 8], dR);
        else wgmma_n128<0, 1, XO(kk), RO(stg, 14336) + k7 * 128, kk != 0>(acc, dX, dR);
      });
      step_end(j == 0 ? stg - 1 : -1);
    };
    const uint32_t slot_off = SM_X + wg * 8192 + 4 * 16384 + (tid & 127) * 16;
    uint4 rv[4];
    auto recv_wait = [&](int i) {
      mbar_wait_cluster(BAR(B_RECV + i), 0);
#pragma unroll
      for (int q = 0; q < 4; q++) rv[q] = lds128(sb + slot_off + (i & 1) * 16384 + q * 2048);
    };
    static_for<6>([&](auto I) {
      constexpr int i = decltype(I)::value;
      const float4 cb1 = lds128f(cb_ + 64 * (17 + 2 * i));
      float4 cbn = cb;
      if (i < 5) cbn = lds128f(cb_ + 64 * (18 + 2 * i));
      if constexpr (i < 3) g2_step(accP, IC<14>{}, IC<0>{}, I);
      else g2_step(accR, IC<15>{}, IC<0>{}, IC<i - 3>{});
      if (i == 0) {
        __syncwarp();
        if (lane == 0) {
          mbar_arrive_remote(BARP(B_XOK));
        }
        reg_fence(accC);
      }
      mish_nb<8 * i, MPAIR>(accC, actC[i].x, actC[i].y, cb, st0, st1);
      mish_nb<8 * i + 4, MPAIR>(accC, actC[i].z, actC[i].w, cb1, st0, st1);
      st_act(8 + i, &actC[i].x);
      if (i == XLSTEP) warp_arrive(B_XL);
      if (i == 0) { o_store(1); o_mma(IC<2>{}); }
      if (i == 1) { o_store(2); o_mma(IC<3>{}); }
      if (i == 2) o_store(3);
      cb = cbn;
    });
    warp_arrive(B_ACT);
    uint4 kp0[4], kp1[4];
    uint4* pdst = scr + 16384 + (ownch * 8 + odd) * 1024 + wg * 512 + (tid & 127);
    const uint4* osrc = scr + 1024 + (16 * odd) * 256 + tid;
    auto o_get = [&](uint4 (&of)[8], int gq) {
      mbar_wait(BAR(B_OFULL), gq);
#pragma unroll
      for (int i = 0; i < 8; i++) of[i] = lds128(sb + SM_X + 6 * 16384 + i * 4096 + tid * 16);
    };
    auto o_check = [&](uint4 (&of)[8], int gq) {
#pragma unroll 1
      for (int tries = 0; tries < (1 << 16); tries++) {
        uint32_t bad = 0;
#pragma unroll
        for (int i = 0; i < 8; i++) bad |= of[i].x ^ tag;
        if (__all_sync(0xffffffffu, (bad & 1u) == 0u)) break;
#pragma unroll
        for (int i = 0; i < 8; i++) of[i] = ld_relaxed128(osrc + (8 * gq + i) * 256);
      }
      __syncwarp();
      if (lane == 0) {
        if (gq == 0) mbar_arrive(BAR(B_XL));
      }
    };
    uint4 ofA[8], ofB[8], p0[4], p2[4];
    static_for<6>([&](auto I) {
      constexpr int i = decltype(I)::value;
      if constexpr (i < 3) g2_step(accP, IC<16>{}, IC<1>{}, I);
      else g2_step(accR, IC<17>{}, IC<1>{}, IC<i - 3>{});
      if (i == 1) mbar_wait_cluster(BAR(B_XOK), 0);
      if (i == 5) bar_sync(11 + wg, 160);
      if (i == 3) {
        reg_fence(accP);
        send_tile<32>(accP, sbp + slot_off, BARP(B_RECV + 0));
      }
      if (i == 4) pack_tile(accP, kp0);
      if (i == 5) o_get(ofA, 0);
    });
    static_for<6>([&](auto I) {
      constexpr int i = decltype(I)::value;
      if constexpr (i < 3) g2_step(accP, IC<18>{}, IC<0>{}, I);
      else g2_step(accP, IC<19>{}, IC<1>{}, IC<i - 3>{});
      if (i == 0) {
        o_check(ofA, 0);
        reg_fence(accR);
        send_tile<32>(accR, sbp + slot_off + 16384, BARP(B_RECV + 1));
      }
      if (i == 1) {
        pack_tile(accR, kp1);
        recv_wait(0);
      }
      if (i == 2) {
        stage_sum(kp0, rv, sb + slot_off, tag);
        warp_arrive(B_EXP + 0);
      }
      if (i == 3) recv_wait(1);
      if (i == 4) {
        stage_sum(kp1, rv, sb + slot_off + 16384, tag);
        warp_arrive(B_EXP + 1);
      }
      if (i == 5) mbar_wait_cluster(BAR(B_PF), 0);
    });

    float accN[32], accO[32];
    auto tile_step = [&](float (&acc)[32], auto S, auto I) {
      constexpr int stg = decltype(S)::value, i = decltype(I)::value, k0 = i < 2 ? 4 * i : 8 + 3 * (i - 2);
      step_begin(i == 0 ? stg : -1);
      static_for<(i < 2 ? 4 : 3)>([&](auto K) {
        constexpr int kk = k0 + decltype(K)::value;
        wgmma_n64<0, 1, XO(kk), RO(stg, 16) + kk * 128, kk != 0>(acc, dX, dR);
      });
      step_end((i == 0 && stg == 20) ? 19 : -1);
    };
    const uint4* psrc = scr + 16384 + sl * 1024 + wg * 512 + (tid & 127);
    auto p_get = [&](uint4 (&v)[4], int i) {
#pragma unroll
      for (int q = 0; q < 4; q++) v[q] = ld_relaxed128(psrc + (size_t)((ownch + 3 - i) & 3) * 8192 + q * 128);
    };
    auto p_check = [&](uint4 (&v)[4], int i) {
#pragma unroll 1
      for (int tries = 0; tries < (1 << 16); tries++) {
        const uint32_t bad = (v[0].x ^ tag) | (v[1].x ^ tag) | (v[2].x ^ tag) | (v[3].x ^ tag);
        if (__all_sync(0xffffffffu, (bad & 1u) == 0u)) break;
#pragma unroll
        for (int q = 0; q < 4; q++) v[q] = ld_relaxed128(psrc + (size_t)((ownch + 3 - i) & 3) * 8192 + q * 128);
      }
    };
    auto p_acc = [&](uint4 (&d)[4], const uint4 (&v)[4]) {
#pragma unroll
      for (int q = 0; q < 4; q++) {
        d[q].x = hadd2(d[q].x, v[q].x); d[q].y = hadd2(d[q].y, v[q].y);
        d[q].z = hadd2(d[q].z, v[q].z); d[q].w = hadd2(d[q].w, v[q].w);
      }
    };
    static_for<4>([&](auto I) {
      constexpr int i = decltype(I)::value;
      tile_step(accN, IC<20>{}, I);
      if (i == 0) {
        reg_fence(accP);
        send_tile<32>(accP, sbp + slot_off, BARP(B_RECV + 2));
      }
      if (i == 1) pack_tile(accP, kp0);
      if (i == 2) o_get(ofB, 1);
      if (i == 3) {
        o_check(ofB, 1);
        mbar_wait_cluster(BAR(B_PF + 1), 0);
      }
    });
    uint32_t xr[16];
    const uint32_t xt_addr = sb + SM_RING + (PH(24) % 3) * SLOT + wg * 8192 + (16 * w + (lane & 7) + 8 * ((lane >> 3) & 1)) * 128;
    static_for<8>([&](auto I) {
      constexpr int i = decltype(I)::value, h = i >> 2, k0 = 2 * (i & 3);
      step_begin((i & 3) == 0 ? 21 + h : -1);
      wgmma_rs_n128<1, RO(21 + h, 16384) + k0 * 128, i != 0>(accR, h ? ofB[k0] : ofA[k0], dR);
      wgmma_rs_n128<1, RO(21 + h, 16384) + (k0 + 1) * 128, 1>(accR, h ? ofB[k0 + 1] : ofA[k0 + 1], dR);
      step_end(i == 0 ? 20 : i == 4 ? 21 : -1);
      if (i == 0) {
        reg_fence(accN);
        send_tile<0>(accN, sbp + slot_off + 16384, BARP(B_RECV + 3));
        recv_wait(2);
      }
      if (i == 1) {
        store_sum(kp0, rv, pdst + 2048 * ((ownch + 3) & 3), tag);
        __syncwarp();
        if (lane == 0) mbar_arrive_remote(BARP(B_SOK));
      }
      if (i == 4) recv_wait(3);
      if (i == 5) {
#pragma unroll
        for (int q = 0; q < 4; q++) {
          p0[q] = rv[q];
          asm volatile("" : "+r"(p0[q].x), "+r"(p0[q].w));
        }
      }
      if (i == 5) p_get(p2, 0);
      if (i == 6) p_get(kp1, 1);
    });
    static_for<4>([&](auto I) {
      constexpr int i = decltype(I)::value;
      tile_step(accO, IC<23>{}, I);
      if (i == 0) {
        mbar_wait_cluster(BAR(B_SOK), 0);
        reg_fence(accR);
        send_tile<32>(accR, sbp + slot_off, BARP(B_RECV + 4));
      }
      if (i == 1) {
        p_check(p2, 0);
        p_acc(p0, p2);
      }
      if (i == 3) {
        p_check(kp1, 1);
        p_acc(p0, kp1);
      }
      if (i == 2) {
        p_get(kp0, 2);
        wait_full(24);
#pragma unroll
        for (int j = 0; j < 4; j++)
          ldsm4(xt_addr + (uint32_t)(((2 * j + st_hi) ^ st_r) << 4), xr[4 * j], xr[4 * j + 1], xr[4 * j + 2], xr[4 * j + 3]);
      }
    });
    recv_wait(4);
    p_check(kp0, 2);
    p_acc(p0, kp0);
    wg_wait<0>();
    reg_fence(accO);
#pragma unroll
    for (int q = 0; q < 4; q++) {
      const uint32_t pa[4] = {p0[q].x, p0[q].y, p0[q].z, p0[q].w};
      const uint32_t sr[4] = {rv[q].x, rv[q].y, rv[q].z, rv[q].w};
#pragma unroll
      for (int j = 0; j < 4; j++) {
        const int i = 8 * q + 2 * j;
        const float h0 = (accO[i] + bf_lo(pa[j])) * (0.5f * kLn2), h1 = (accO[i + 1] + bf_hi(pa[j])) * (0.5f * kLn2);
        const float g0 = fmaf(h0, tanhf_approx(h0), h0), g1 = fmaf(h1, tanhf_approx(h1), h1);
        const float s0 = accR[i] + bf_lo(sr[j]), s1 = accR[i + 1] + bf_hi(sr[j]);
        const uint32_t xv = xr[i >> 1];
        xr[i >> 1] = pack2(fmaf(s0, g0, bf_lo(xv)), fmaf(s1, g1, bf_hi(xv)));
      }
      stsm4(xt_addr + (uint32_t)(((2 * q + st_hi) ^ st_r) << 4), xr[4 * q], xr[4 * q + 1], xr[4 * q + 2], xr[4 * q + 3]);
    }
    __syncwarp();
    {
      const int r0 = lane >> 3, ch = lane & 7;
      const uint32_t base = sb + SM_RING + (PH(24) % 3) * SLOT + wg * 8192 + (16 * w + r0) * 128;
      uint4* dst = reinterpret_cast<uint4*>(out + (size_t)(128 * rb + 64 * wg + 16 * w + r0) * 512 + 64 * sl) + ch;
      uint4 v[4];
#pragma unroll
      for (int j = 0; j < 4; j++) v[j] = lds128(base + j * 512 + (uint32_t)((ch ^ ((r0 + 4 * j) & 7)) << 4));
#pragma unroll
      for (int j = 0; j < 4; j++) dst[j * 4 * 64] = v[j];
    }
  }
#undef BAR
}

typedef CUresult (*EncFn)(CUtensorMap*, CUtensorMapDataType, cuuint32_t, void*, const cuuint64_t*, const cuuint64_t*,
                          const cuuint32_t*, const cuuint32_t*, CUtensorMapInterleave, CUtensorMapSwizzle,
                          CUtensorMapL2promotion, CUtensorMapFloatOOBfill);

void make_map(EncFn enc, CUtensorMap* m, const void* p, int rows, int cols, int box_rows) {
  cuuint64_t gd[2] = {(cuuint64_t)cols, (cuuint64_t)rows};
  cuuint64_t gs[1] = {(cuuint64_t)cols * 2};
  cuuint32_t box[2] = {64, (cuuint32_t)box_rows};
  cuuint32_t es[2] = {1, 1};
  enc(m, CU_TENSOR_MAP_DATA_TYPE_BFLOAT16, 2, const_cast<void*>(p), gd, gs, box, es, CU_TENSOR_MAP_INTERLEAVE_NONE,
      CU_TENSOR_MAP_SWIZZLE_128B, CU_TENSOR_MAP_L2_PROMOTION_L2_128B, CU_TENSOR_MAP_FLOAT_OOB_FILL_NONE);
}

}

extern "C" void kernel_launch(void* const* d_in, const int* in_sizes, int n_in, void* d_out, int out_size) {
  const bf16* x = (const bf16*)d_in[0];
  const bf16* wqkv = (const bf16*)d_in[1];
  const bf16* wo = (const bf16*)d_in[2];
  const bf16* w1 = (const bf16*)d_in[4];
  const bf16* b1 = (const bf16*)d_in[5];
  const bf16* w2 = (const bf16*)d_in[6];
  bf16* out = (bf16*)d_out;

  static EncFn enc = nullptr;
  if (!enc) {
    void* fn = nullptr;
    cudaDriverEntryPointQueryResult qr;
    cudaGetDriverEntryPoint("cuTensorMapEncodeTiled", &fn, cudaEnableDefault, &qr);
    enc = (EncFn)fn;
    cudaFuncSetAttribute(fused_kernel, cudaFuncAttributeMaxDynamicSharedMemorySize, SM_TOTAL);
  }
  CUtensorMap tm_x, tm_wqkv, tm_w1, tm_w2, tm_wo;
  make_map(enc, &tm_x, x, 2048, 512, 128);
  make_map(enc, &tm_wqkv, wqkv, 512, 1536, 64);
  make_map(enc, &tm_w1, w1, 512, 1792, 128);
  make_map(enc, &tm_w2, w2, 1792, 512, 112);
  make_map(enc, &tm_wo, wo, 512, 512, 128);
  cudaLaunchConfig_t cfg = {};
  cfg.gridDim = dim3(128);
  cfg.blockDim = dim3(384);
  cfg.dynamicSmemBytes = SM_TOTAL;
  cfg.stream = cudaStreamPerThread;
  cudaLaunchAttribute at[1];
  at[0].id = cudaLaunchAttributeClusterDimension;
  at[0].val.clusterDim.x = 2;
  at[0].val.clusterDim.y = 1;
  at[0].val.clusterDim.z = 1;
  cfg.attrs = at;
  cfg.numAttrs = 1;
  cudaLaunchKernelEx(&cfg, fused_kernel, tm_x, tm_wqkv, tm_w1, tm_w2, tm_wo, x, wqkv, w1, b1, w2, wo, out);
}
```
